```python
import torch

def _softmax(x, axis=-1):
    return torch.softmax(x, dim=axis)
def _gelu(x):
    return torch.nn.functional.gelu(x, approximate="tanh")
def _silu(x):
    return torch.nn.functional.silu(x)
def _sigmoid(x):
    return torch.sigmoid(x)
def _layernorm(x, axis=-1, eps=1e-5):
    m = x.mean(dim=axis, keepdim=True)
    v = x.var(dim=axis, keepdim=True, unbiased=False)
    return (x - m) / torch.sqrt(v + eps)
def _scatter_add(tgt, idx, src, axis=0):
    return tgt.clone().index_add_(axis, idx, src)
def _segment_sum(src, seg, n):
    out = torch.zeros((n,) + src.shape[1:], dtype=src.dtype)
    return out.index_add_(0, seg, src)
def _pad(x, pw):
    flat = tuple(v for pair in reversed(pw) for v in pair)
    return torch.nn.functional.pad(x, flat)

kernel_name = 'standalone__gqa_block_cached__decode'

def setup_inputs():

    _w = (lambda a: (lambda t: t.to(torch.bfloat16) if t.is_floating_point() else t)(torch.as_tensor(a)))
    B, Sq, D = 8, 1, 512
    Hq, Hkv, Sk, Dh = 32, 8, 4096, 128
    assert Hq % Hkv == 0, (Hq, Hkv)
    return {
        "x": _w((lambda *s: torch.randn(*s, dtype=torch.bfloat16) * 0.8)(B, Sq, D)),
        "k_cache": _w((lambda *s: torch.randn(*s, dtype=torch.bfloat16) * 0.8)(B, Hkv, Sk, Dh)),
        "v_cache": _w((lambda *s: torch.randn(*s, dtype=torch.bfloat16) * 0.05)(B, Hkv, Sk, Dh)),
        "wq": _w((lambda *s: torch.randn(*s, dtype=torch.bfloat16) * 0.8)(D, Hq * Dh) * (D ** -0.5)),
        "wo": _w((lambda *s: torch.randn(*s, dtype=torch.bfloat16) * 0.05)(Hq * Dh, D) * ((Hq * Dh) ** -0.5)),
    }

def reference(x, k_cache, v_cache, wq, wo):
    B, Sq, D = x.shape
    Hq, Dh = 32, 128
    Hkv = k_cache.shape[1]
    rep = Hq // Hkv
    q = (lambda x, *d: x.permute(*d))((x @ wq).reshape(B, Sq, Hq, Dh), 0, 2, 1, 3)
    k = (lambda x, n, axis: torch.repeat_interleave(x, n, dim=axis))(k_cache, rep, axis=1)
    v = (lambda x, n, axis: torch.repeat_interleave(x, n, dim=axis))(v_cache, rep, axis=1)
    scores = torch.einsum("bhqd,bhkd->bhqk", q, k) * (Dh ** -0.5)
    p = _softmax(scores, axis=-1)
    o = torch.einsum("bhqk,bhkd->bhqd", p, v)
    return (lambda x, *d: x.permute(*d))(o, 0, 2, 1, 3).reshape(B, Sq, Hq * Dh) @ wo
```

```cpp
#include <cuda_runtime.h>
#include <cuda_bf16.h>
#include <cuda.h>
#include <stdint.h>

namespace {

constexpr int kB = 8, kD = 512, kHQ = 32, kHKV = 8, kSK = 4096, kDH = 128;
constexpr int kNCTA = 128;
constexpr int kKeysPerCta = 2048;
constexpr int kTile = 128;
constexpr int kNTiles = kKeysPerCta / kTile;
constexpr int kStageBytes = kTile * kDH * 2;
#define NSTAGE 6
#define POLL_NS 20
#define WO_POS 33
#define WINDOW 2
constexpr int kNStage = NSTAGE;
constexpr int kWindow = WINDOW;
constexpr int kNLoads = 2 * kNTiles + 2;
constexpr int kConsWarps = 8;
constexpr int kConsThreads = kConsWarps * 32;
constexpr int kThreads = kConsThreads + 32;

constexpr int kSmemStages = 0;
constexpr int kSmemScr = kNStage * kStageBytes;
constexpr int kScrRed  = kSmemScr;
constexpr int kScrPart = kSmemScr;
constexpr int kScrM    = kScrPart + 8 * 4 * 136 * 4;
constexpr int kScrOb   = kScrM + 8 * 4 * 8;
constexpr int kScrQs   = kScrOb + 8 * 68 * 4;
constexpr int kSmemBars = kScrQs + 4 * 68 * 4;
constexpr int kSmemTotal = kSmemBars + 16 * kNStage;
static_assert(kSmemTotal <= 232448, "smem budget");

constexpr float kScaleLog2 = 0.08838834764831845f * 1.4426950408889634f;

struct Scratch {
    uint2 q[kB * 2048];
    uint2 o[kHQ * kB * 2 * 64];
    uint4 s[kHQ * kB * 2];
    uint2 p[kNCTA * 1024];
    uint32_t epoch[kNCTA];
};
__device__ Scratch g_scratch;

__device__ __forceinline__ uint32_t smem_u32(const void* p) {
    return (uint32_t)__cvta_generic_to_shared(p);
}
__device__ __forceinline__ void mbar_init(uint32_t bar, uint32_t count) {
    asm volatile("mbarrier.init.shared::cta.b64 [%0], %1;" ::"r"(bar), "r"(count) : "memory");
}
__device__ __forceinline__ void mbar_expect_tx(uint32_t bar, uint32_t bytes) {
    asm volatile("mbarrier.arrive.expect_tx.shared::cta.b64 _, [%0], %1;" ::"r"(bar), "r"(bytes) : "memory");
}
__device__ __forceinline__ void mbar_arrive(uint32_t bar) {
    asm volatile("mbarrier.arrive.shared::cta.b64 _, [%0];" ::"r"(bar) : "memory");
}
__device__ __forceinline__ bool mbar_try_wait(uint32_t bar, uint32_t parity) {
    uint32_t ok;
    asm volatile(
        "{\n\t.reg .pred p;\n\t"
        "mbarrier.try_wait.parity.shared::cta.b64 p, [%1], %2;\n\t"
        "selp.u32 %0, 1, 0, p;\n\t}"
        : "=r"(ok) : "r"(bar), "r"(parity) : "memory");
    return ok != 0;
}
__device__ __forceinline__ void mbar_wait(uint32_t bar, uint32_t parity) {
    uint32_t spins = 0;
    while (!mbar_try_wait(bar, parity)) {
        if (++spins > (1u << 24)) __trap();
    }
}
__device__ __forceinline__ void tma_load_2d(uint32_t dst, const CUtensorMap* map, int c0, int c1,
                                            uint32_t bar, uint64_t policy) {
    asm volatile(
        "cp.async.bulk.tensor.2d.shared::cluster.global.mbarrier::complete_tx::bytes.L2::cache_hint "
        "[%0], [%1, {%3, %4}], [%2], %5;"
        ::"r"(dst), "l"(map), "r"(bar), "r"(c0), "r"(c1), "l"(policy) : "memory");
}
__device__ __forceinline__ void cons_bar() { asm volatile("bar.sync 1, 256;" ::: "memory"); }

__device__ __forceinline__ void ldsm_x4(uint32_t addr, uint32_t& r0, uint32_t& r1, uint32_t& r2, uint32_t& r3) {
    asm volatile("ldmatrix.sync.aligned.m8n8.x4.shared.b16 {%0,%1,%2,%3}, [%4];"
                 : "=r"(r0), "=r"(r1), "=r"(r2), "=r"(r3) : "r"(addr) : "memory");
}
__device__ __forceinline__ void ldsm_x4_t(uint32_t addr, uint32_t& r0, uint32_t& r1, uint32_t& r2, uint32_t& r3) {
    asm volatile("ldmatrix.sync.aligned.m8n8.x4.trans.shared.b16 {%0,%1,%2,%3}, [%4];"
                 : "=r"(r0), "=r"(r1), "=r"(r2), "=r"(r3) : "r"(addr) : "memory");
}
__device__ __forceinline__ void mma_bf16(float (&c)[4], uint32_t a0, uint32_t a1, uint32_t a2, uint32_t a3,
                                         uint32_t b0, uint32_t b1) {
    asm volatile(
        "mma.sync.aligned.m16n8k16.row.col.f32.bf16.bf16.f32 {%0,%1,%2,%3}, {%4,%5,%6,%7}, {%8,%9}, {%0,%1,%2,%3};"
        : "+f"(c[0]), "+f"(c[1]), "+f"(c[2]), "+f"(c[3])
        : "r"(a0), "r"(a1), "r"(a2), "r"(a3), "r"(b0), "r"(b1));
}
__device__ __forceinline__ uint32_t movmatrix_t(uint32_t a) {
    uint32_t d;
    asm volatile("movmatrix.sync.aligned.m8n8.trans.b16 %0, %1;" : "=r"(d) : "r"(a));
    return d;
}
__device__ __forceinline__ uint32_t pack_bf16(float lo, float hi) {
    uint32_t d;
    asm("cvt.rn.bf16x2.f32 %0, %1, %2;" : "=r"(d) : "f"(hi), "f"(lo));
    return d;
}
__device__ __forceinline__ float bf16_lo(uint32_t v) { return __uint_as_float(v << 16); }
__device__ __forceinline__ float bf16_hi(uint32_t v) { return __uint_as_float(v & 0xffff0000u); }
__device__ __forceinline__ float ex2(float x) {
    float y;
    asm("ex2.approx.ftz.f32 %0, %1;" : "=f"(y) : "f"(x));
    return y;
}
__device__ __forceinline__ float rcp(float x) {
    float y;
    asm("rcp.approx.ftz.f32 %0, %1;" : "=f"(y) : "f"(x));
    return y;
}
__device__ __forceinline__ uint2 ldg64(const void* p) {
    uint2 v;
    asm volatile("ld.global.nc.L1::no_allocate.v2.u32 {%0,%1}, [%2];" : "=r"(v.x), "=r"(v.y) : "l"(p));
    return v;
}
__device__ __forceinline__ uint4 ldg128(const void* p) {
    uint4 v;
    asm volatile("ld.global.nc.L1::no_allocate.v4.u32 {%0,%1,%2,%3}, [%4];"
                 : "=r"(v.x), "=r"(v.y), "=r"(v.z), "=r"(v.w) : "l"(p));
    return v;
}
__device__ __forceinline__ void ll_store(uint2* p, uint32_t payload, uint32_t tag) {
    asm volatile("{\n\t.reg .b64 v;\n\tmov.b64 v, {%1, %2};\n\tst.relaxed.gpu.global.b64 [%0], v;\n\t}"
                 ::"l"(p), "r"(payload), "r"(tag) : "memory");
}
__device__ __forceinline__ void ll_store2(void* p, uint32_t p0, uint32_t p1, uint32_t tag) {
    asm volatile("{\n\t.reg .b64 v, w;\n\tmov.b64 v, {%1, %3};\n\tmov.b64 w, {%2, %3};\n\t"
                 "st.relaxed.gpu.global.v2.b64 [%0], {v, w};\n\t}"
                 ::"l"(p), "r"(p0), "r"(p1), "r"(tag) : "memory");
}
__device__ __forceinline__ void ll_load(const void* p, uint32_t& v, uint32_t& t) {
    asm volatile("{\n\t.reg .b64 a;\n\tld.relaxed.gpu.global.b64 a, [%2];\n\tmov.b64 {%0, %1}, a;\n\t}"
                 : "=r"(v), "=r"(t) : "l"(p) : "memory");
}
__device__ __forceinline__ void ll_load2(const void* p, uint32_t& v0, uint32_t& t0, uint32_t& v1, uint32_t& t1) {
    asm volatile("{\n\t.reg .b64 a, b;\n\tld.relaxed.gpu.global.v2.b64 {a, b}, [%4];\n\t"
                 "mov.b64 {%0, %1}, a;\n\tmov.b64 {%2, %3}, b;\n\t}"
                 : "=r"(v0), "=r"(t0), "=r"(v1), "=r"(t1) : "l"(p) : "memory");
}

#define TDECL
#define TSTAMP(i) do { } while (0)
#define TDUMP() do { } while (0)

constexpr uint32_t kSpinLimit = 1u << 22;

__global__ void __launch_bounds__(kThreads, 1)
gqa_decode_kernel(const __grid_constant__ CUtensorMap tmK, const __grid_constant__ CUtensorMap tmV,
                  const __grid_constant__ CUtensorMap tmWq, const __grid_constant__ CUtensorMap tmWo,
                  const __nv_bfloat16* __restrict__ x, __nv_bfloat16* __restrict__ out, Scratch* __restrict__ scr) {
    extern __shared__ __align__(1024) uint8_t smem[];
    const uint32_t sbase = smem_u32(smem);
    const int tid = threadIdx.x;
    const int warp = tid >> 5, lane = tid & 31;
    const int cta = blockIdx.x;
    const int hkv = cta >> 4;
    const int bat = (cta >> 1) & 7;
    const int half = cta & 1;
    const int oh = cta >> 2;
    const int oc = cta & 3;
    const uint32_t bar_full = sbase + kSmemBars;
    const uint32_t bar_empty = bar_full + 8 * kNStage;

    if (warp == kConsWarps) {
        if (lane == 0) {
#pragma unroll
            for (int s = 0; s < kNStage; s++) {
                mbar_init(bar_full + 8 * s, 1);
                mbar_init(bar_empty + 8 * s, kConsWarps);
            }
            asm volatile("fence.mbarrier_init.release.cluster;" ::: "memory");
            asm volatile("fence.proxy.async.shared::cta;" ::: "memory");
        }
        uint64_t policy;
        asm volatile("createpolicy.fractional.L2::evict_first.b64 %0, 1.0;" : "=l"(policy));
        const int row0 = (bat * kHKV + hkv) * kSK + half * kKeysPerCta;
        constexpr int kRowStep = kTile;
        auto issue = [&](int i, int s) {
            const uint32_t dst = sbase + kSmemStages + s * kStageBytes;
            const uint32_t bar = bar_full + 8 * s;
            mbar_expect_tx(bar, kStageBytes);
            if (i == 0) {
                tma_load_2d(dst, &tmWq, cta * 32, 0, bar, policy);
                tma_load_2d(dst + 16384, &tmWq, cta * 32, 256, bar, policy);
            } else if (i != WO_POS) {
                const int kv = (i > WO_POS) ? i - 2 : i - 1;
                const CUtensorMap* map = (kv & 1) ? &tmV : &tmK;
                const int row = row0 + (kv >> 1) * kRowStep;
                tma_load_2d(dst, map, 0, row, bar, policy);
                tma_load_2d(dst + 16384, map, 64, row, bar, policy);
            } else {
                tma_load_2d(dst, &tmWo, oc * 128, oh * 128, bar, policy);
                tma_load_2d(dst + 16384, &tmWo, oc * 128 + 64, oh * 128, bar, policy);
            }
        };
        if (lane == 0) {
#pragma unroll
            for (int i = 0; i < kWindow; i++) issue(i, i);
        }
        __syncthreads();
        if (lane == 0) {
            int s = kWindow % kNStage, ph = (kWindow >= kNStage) ? 0 : 1;
            int ws = 0, wph = 0;
            for (int i = kWindow; i < kNLoads; i++) {
                mbar_wait(bar_empty + 8 * s, ph);
                mbar_wait(bar_full + 8 * ws, wph);
                issue(i, s);
                if (++s == kNStage) { s = 0; ph ^= 1; }
                if (++ws == kNStage) { ws = 0; wph ^= 1; }
            }
        }
        return;
    }

    const int g = lane >> 2, j = lane & 3;
    TDECL
    TSTAMP(0);

    {
        if (tid < 128) ll_store(&scr->q[(tid >> 4) * 2048 + cta * 16 + (tid & 15)], 0u, 0u);
        ll_store(&scr->o[(((hkv * 4 + (tid >> 6)) * kB + bat) * 2 + half) * 64 + (tid & 63)], 0u, 0u);
        if ((tid & 63) == 0) ll_store2(&scr->s[((hkv * 4 + (tid >> 6)) * kB + bat) * 2 + half], 0u, 0u, 0u);
        uint2* pp = &scr->p[((tid >> 5) * 16 + oc * 4) * 1024 + oh * 32 + (tid & 31)];
#pragma unroll
        for (int q = 0; q < 4; q++) ll_store(pp + q * 1024, 0u, 0u);
    }
    uint32_t xb[4][2];
    {
        const uint32_t* xr = reinterpret_cast<const uint32_t*>(x + g * kD + warp * 64);
#pragma unroll
        for (int s = 0; s < 4; s++) {
            xb[s][0] = __ldg(xr + s * 8 + j);
            xb[s][1] = __ldg(xr + s * 8 + 4 + j);
        }
    }
    const uint32_t tag = __ldcg(&scr->epoch[cta]) + 1;
    __syncthreads();
    TSTAMP(1);
    int stage = 0, phase = 0;
    {
        float qa[2][4] = {{0.f, 0.f, 0.f, 0.f}, {0.f, 0.f, 0.f, 0.f}};
        mbar_wait(bar_full, 0);
#pragma unroll
        for (int s = 0; s < 4; s++) {
            const int row = warp * 64 + s * 16 + (lane & 7) + ((lane >> 4) << 3);
#pragma unroll
            for (int mt = 0; mt < 2; mt++) {
                const int c = 2 * mt + ((lane >> 3) & 1);
                uint32_t a0, a1, a2, a3;
                ldsm_x4_t(sbase + kSmemStages + row * 64 + ((c ^ ((row >> 1) & 3)) << 4), a0, a1, a2, a3);
                mma_bf16(qa[mt], a0, a1, a2, a3, xb[s][0], xb[s][1]);
            }
        }
        __syncwarp();
        if (lane == 0) mbar_arrive(bar_empty);
        stage = 1;
        TSTAMP(2);
        float* red = reinterpret_cast<float*>(smem + kScrRed) + warp * (8 * 36);
#pragma unroll
        for (int mt = 0; mt < 2; mt++) {
            red[(2 * j) * 36 + mt * 16 + g] = qa[mt][0];
            red[(2 * j + 1) * 36 + mt * 16 + g] = qa[mt][1];
            red[(2 * j) * 36 + mt * 16 + g + 8] = qa[mt][2];
            red[(2 * j + 1) * 36 + mt * 16 + g + 8] = qa[mt][3];
        }
    }
    cons_bar();
    if (tid < 128) {
        const int b = tid >> 4, cp = tid & 15;
        const float* red = reinterpret_cast<const float*>(smem + kScrRed) + b * 36 + 2 * cp;
        float s0 = 0.f, s1 = 0.f;
#pragma unroll
        for (int w = 0; w < 8; w++) {
            const float2 v = *reinterpret_cast<const float2*>(red + w * (8 * 36));
            s0 += v.x; s1 += v.y;
        }
        ll_store(&scr->q[b * 2048 + cta * 16 + cp], pack_bf16(s0, s1), tag);
    }
    TSTAMP(3);
    {
        const uint2* p = &scr->q[bat * 2048 + hkv * 256 + tid];
        uint32_t v, t, spins = 0;
        ll_load(p, v, t);
        while (t != tag) {
            if (++spins > kSpinLimit) __trap();
            __nanosleep(40);
            ll_load(p, v, t);
        }
        reinterpret_cast<uint32_t*>(smem + kScrQs)[(tid >> 6) * 68 + (tid & 63)] = v;
    }
    cons_bar();
    TSTAMP(4);
    uint32_t qb[8][2];
    {
        const uint32_t* qs = reinterpret_cast<const uint32_t*>(smem + kScrQs);
#pragma unroll
        for (int s = 0; s < 8; s++) {
            qb[s][0] = (g < 4) ? qs[g * 68 + 8 * s + j] : 0u;
            qb[s][1] = (g < 4) ? qs[g * 68 + 8 * s + 4 + j] : 0u;
        }
    }

    float oacc[8][4];
#pragma unroll
    for (int t = 0; t < 8; t++) { oacc[t][0] = oacc[t][1] = oacc[t][2] = oacc[t][3] = 0.f; }
    float lacc[4] = {0.f, 0.f, 0.f, 0.f};
    float m0 = -INFINITY, m1 = -INFINITY;

    uint32_t koff[4], voff[4];
    {
        const uint32_t krow = warp * 16 + (lane & 15);
        const uint32_t ky = ((lane >> 4) ^ (lane & 7)) << 4;
        const uint32_t vrow = warp * 16 + (lane & 7) + ((lane >> 4) << 3);
        const uint32_t vy = (((lane >> 3) & 1) ^ (lane & 7)) << 4;
#pragma unroll
        for (int s = 0; s < 4; s++) {
            koff[s] = krow * 128 + (ky ^ (s << 5));
            voff[s] = vrow * 128 + (vy ^ (s << 5));
        }
    }

    int wo_stage = 0, wo_phase = 0;
#pragma unroll 1
    for (int t = 0; t < kNTiles; t++) {
        if (WO_POS < 33 && t == (WO_POS - 1) / 2) {
            wo_stage = stage; wo_phase = phase;
            if (++stage == kNStage) { stage = 0; phase ^= 1; }
        }
        float sc[2][4] = {{0.f, 0.f, 0.f, 0.f}, {0.f, 0.f, 0.f, 0.f}};
        {
            mbar_wait(bar_full + 8 * stage, phase);
            const uint32_t kb = sbase + kSmemStages + stage * kStageBytes;
#pragma unroll
            for (int s = 0; s < 8; s++) {
                uint32_t a0, a1, a2, a3;
                ldsm_x4(kb + koff[s & 3] + (s >> 2) * 16384, a0, a1, a2, a3);
                mma_bf16(sc[s & 1], a0, a1, a2, a3, qb[s][0], qb[s][1]);
            }
            __syncwarp();
            if (lane == 0) mbar_arrive(bar_empty + 8 * stage);
            if (++stage == kNStage) { stage = 0; phase ^= 1; }
        }
        const float s0 = sc[0][0] + sc[1][0], s1 = sc[0][1] + sc[1][1];
        const float s2 = sc[0][2] + sc[1][2], s3 = sc[0][3] + sc[1][3];
        float t0 = fmaxf(s0, s2), t1 = fmaxf(s1, s3);
#pragma unroll
        for (int o = 4; o < 32; o <<= 1) {
            t0 = fmaxf(t0, __shfl_xor_sync(0xffffffffu, t0, o));
            t1 = fmaxf(t1, __shfl_xor_sync(0xffffffffu, t1, o));
        }
        const float mn0 = fmaxf(m0, t0), mn1 = fmaxf(m1, t1);
        const float al0 = ex2((m0 - mn0) * kScaleLog2), al1 = ex2((m1 - mn1) * kScaleLog2);
        m0 = mn0; m1 = mn1;
        const float b0 = mn0 * kScaleLog2, b1 = mn1 * kScaleLog2;
        const float p0 = ex2(fmaf(s0, kScaleLog2, -b0)), p1 = ex2(fmaf(s1, kScaleLog2, -b1));
        const float p2 = ex2(fmaf(s2, kScaleLog2, -b0)), p3 = ex2(fmaf(s3, kScaleLog2, -b1));
        const uint32_t pb0 = movmatrix_t(pack_bf16(p0, p1));
        const uint32_t pb1 = movmatrix_t(pack_bf16(p2, p3));
#pragma unroll
        for (int mt = 0; mt < 8; mt++) {
            oacc[mt][0] *= al0; oacc[mt][1] *= al1; oacc[mt][2] *= al0; oacc[mt][3] *= al1;
        }
        lacc[0] *= al0; lacc[1] *= al1;
        mma_bf16(lacc, 0x3f803f80u, 0x3f803f80u, 0x3f803f80u, 0x3f803f80u, pb0, pb1);
        {
            mbar_wait(bar_full + 8 * stage, phase);
            const uint32_t vb = sbase + kSmemStages + stage * kStageBytes;
#pragma unroll
            for (int mt = 0; mt < 8; mt++) {
                uint32_t a0, a1, a2, a3;
                ldsm_x4_t(vb + voff[mt & 3] + (mt >> 2) * 16384, a0, a1, a2, a3);
                mma_bf16(oacc[mt], a0, a1, a2, a3, pb0, pb1);
            }
            __syncwarp();
            if (lane == 0) mbar_arrive(bar_empty + 8 * stage);
            if (++stage == kNStage) { stage = 0; phase ^= 1; }
        }
    }
    TSTAMP(7);
    if (WO_POS == 33) { wo_stage = stage; wo_phase = phase; }

    {
        float* part = reinterpret_cast<float*>(smem + kScrPart) + warp * (4 * 136);
        float2* ml = reinterpret_cast<float2*>(smem + kScrM) + warp * 4;
        if (j < 2) {
#pragma unroll
            for (int mt = 0; mt < 8; mt++) {
                part[(2 * j) * 136 + mt * 16 + g] = oacc[mt][0];
                part[(2 * j + 1) * 136 + mt * 16 + g] = oacc[mt][1];
                part[(2 * j) * 136 + mt * 16 + g + 8] = oacc[mt][2];
                part[(2 * j + 1) * 136 + mt * 16 + g + 8] = oacc[mt][3];
            }
            if (g == 0) {
                ml[2 * j] = make_float2(m0, lacc[0]);
                ml[2 * j + 1] = make_float2(m1, lacc[1]);
            }
        }
    }
    cons_bar();
    TSTAMP(8);
    {
        const int hl = tid >> 6, pr = tid & 63;
        const float* part = reinterpret_cast<const float*>(smem + kScrPart) + hl * 136 + 2 * pr;
        const float2* ml = reinterpret_cast<const float2*>(smem + kScrM) + hl;
        float mw[8], lw[8];
        float M = -INFINITY;
#pragma unroll
        for (int w = 0; w < 8; w++) {
            const float2 v = ml[w * 4];
            mw[w] = v.x; lw[w] = v.y;
            M = fmaxf(M, v.x);
        }
        float L = 0.f, o0 = 0.f, o1 = 0.f;
#pragma unroll
        for (int w = 0; w < 8; w++) {
            const float sc = ex2((mw[w] - M) * kScaleLog2);
            const float2 v = *reinterpret_cast<const float2*>(part + w * (4 * 136));
            L = fmaf(lw[w], sc, L);
            o0 = fmaf(v.x, sc, o0);
            o1 = fmaf(v.y, sc, o1);
        }
        const float inv = rcp(L);
        const int slot = ((hkv * 4 + hl) * kB + bat) * 2 + half;
        ll_store(&scr->o[slot * 64 + pr], pack_bf16(o0 * inv, o1 * inv), tag);
        if (pr == 0) ll_store2(&scr->s[slot], __float_as_uint(M), __float_as_uint(L), tag);
    }
    TSTAMP(9);

    {
        const int b = tid >> 5, pp = (tid & 31) * 2;
        const uint2* p0 = &scr->o[((oh * kB + b) * 2) * 64 + pp];
        const uint4* ps = &scr->s[(oh * kB + b) * 2];
        uint32_t va0, va1, vb0, vb1, sm0, sl0, sm1, sl1;
        uint32_t spins = 0;
        while (true) {
            uint32_t t0, t1, t2, t3, t4, t5, t6, t7;
            ll_load2(p0, va0, t0, va1, t1);
            ll_load2(p0 + 64, vb0, t2, vb1, t3);
            ll_load2(ps, sm0, t4, sl0, t5);
            ll_load2(ps + 1, sm1, t6, sl1, t7);
            const uint32_t bad = (t0 ^ tag) | (t1 ^ tag) | (t2 ^ tag) | (t3 ^ tag) | (t4 ^ tag) | (t5 ^ tag) |
                                 (t6 ^ tag) | (t7 ^ tag);
            if (__all_sync(0xffffffffu, bad == 0)) break;
            while (((t4 ^ tag) | (t5 ^ tag) | (t6 ^ tag) | (t7 ^ tag)) != 0) {
                if (++spins > kSpinLimit) __trap();
                __nanosleep(POLL_NS);
                ll_load2(ps, sm0, t4, sl0, t5);
                ll_load2(ps + 1, sm1, t6, sl1, t7);
            }
            if (++spins > kSpinLimit) __trap();
        }
        const float mA = __uint_as_float(sm0), lA = __uint_as_float(sl0);
        const float mB = __uint_as_float(sm1), lB = __uint_as_float(sl1);
        const float M = fmaxf(mA, mB);
        float wA = lA * ex2((mA - M) * kScaleLog2), wB = lB * ex2((mB - M) * kScaleLog2);
        const float inv = rcp(wA + wB);
        wA *= inv; wB *= inv;
        uint2 r;
        r.x = pack_bf16(wA * bf16_lo(va0) + wB * bf16_lo(vb0), wA * bf16_hi(va0) + wB * bf16_hi(vb0));
        r.y = pack_bf16(wA * bf16_lo(va1) + wB * bf16_lo(vb1), wA * bf16_hi(va1) + wB * bf16_hi(vb1));
        uint32_t* ob = reinterpret_cast<uint32_t*>(smem + kScrOb);
        *reinterpret_cast<uint2*>(ob + b * 68 + pp) = r;
    }
    TSTAMP(10);
    uint32_t wa[8][4];
    {
        mbar_wait(bar_full + 8 * wo_stage, wo_phase);
        TSTAMP(15);
        const uint32_t c = ((2 * warp) & 7) + ((lane >> 3) & 1);
        const uint32_t rr = (lane & 7) + ((lane >> 4) << 3);
        const uint32_t base = sbase + kSmemStages + wo_stage * kStageBytes + (warp >> 2) * 16384 + rr * 128 +
                              ((c ^ (lane & 7)) << 4);
#pragma unroll
        for (int s = 0; s < 8; s++) ldsm_x4_t(base + s * 16 * 128, wa[s][0], wa[s][1], wa[s][2], wa[s][3]);
    }
    cons_bar();
    TSTAMP(11);
    {
        const uint32_t* ob = reinterpret_cast<const uint32_t*>(smem + kScrOb) + g * 68 + j;
        float c[4][4];
#pragma unroll
        for (int i = 0; i < 4; i++) { c[i][0] = c[i][1] = c[i][2] = c[i][3] = 0.f; }
#pragma unroll
        for (int s = 0; s < 8; s++)
            mma_bf16(c[s & 3], wa[s][0], wa[s][1], wa[s][2], wa[s][3], ob[8 * s], ob[8 * s + 4]);
        const int col = oc * 128 + warp * 16 + g;
        uint2* dst = &scr->p[(2 * j * 16 + (col >> 5)) * 1024 + oh * 32 + (col & 31)];
#pragma unroll
        for (int e = 0; e < 4; e++) {
            const float v = (c[0][e] + c[1][e]) + (c[2][e] + c[3][e]);
            ll_store(dst + (e & 1) * (16 * 1024) + (e >> 1) * 8, __float_as_uint(v), tag);
        }
    }
    TSTAMP(12);

    {
        const uint2* p = &scr->p[cta * 1024 + warp * 128 + lane];
        uint32_t v0, v1, v2, v3, spins = 0;
        while (true) {
            uint32_t t0, t1, t2, t3;
            ll_load(p, v0, t0);
            ll_load(p + 32, v1, t1);
            ll_load(p + 64, v2, t2);
            ll_load(p + 96, v3, t3);
            const uint32_t bad = (t0 ^ tag) | (t1 ^ tag) | (t2 ^ tag) | (t3 ^ tag);
            if (__all_sync(0xffffffffu, bad == 0)) break;
            if (lane < 4) {
                uint32_t v, t;
                const uint2* pw = p - lane + lane * 32;
                ll_load(pw, v, t);
                while (t != tag) {
                    if (++spins > kSpinLimit) __trap();
                    __nanosleep(POLL_NS);
                    ll_load(pw, v, t);
                }
            }
            __syncwarp();
            if (++spins > kSpinLimit) __trap();
        }
        TSTAMP(13);
        float* fr = reinterpret_cast<float*>(smem + kScrPart);
        fr[warp * 32 + lane] = (__uint_as_float(v0) + __uint_as_float(v1)) + (__uint_as_float(v2) + __uint_as_float(v3));
        cons_bar();
        if (warp == 0) {
            float z = 0.f;
#pragma unroll
            for (int w = 0; w < 8; w++) z += fr[w * 32 + lane];
            out[(cta >> 4) * kD + (cta & 15) * 32 + lane] = __float2bfloat16(z);
            if (lane == 0) scr->epoch[cta] = tag;
        }
    }
    TSTAMP(14);
    TDUMP();
}

typedef CUresult (*EncodeTiledFn)(CUtensorMap*, CUtensorMapDataType, cuuint32_t, void*, const cuuint64_t*,
                                  const cuuint64_t*, const cuuint32_t*, const cuuint32_t*, CUtensorMapInterleave,
                                  CUtensorMapSwizzle, CUtensorMapL2promotion, CUtensorMapFloatOOBfill);

bool make_map(EncodeTiledFn fn, CUtensorMap* map, const void* ptr, uint64_t cols, uint64_t rows, uint32_t box_cols,
              uint32_t box_rows, CUtensorMapSwizzle swz, CUtensorMapL2promotion promo) {
    cuuint64_t dims[2] = {(cuuint64_t)cols, (cuuint64_t)rows};
    cuuint64_t strides[1] = {(cuuint64_t)cols * 2};
    cuuint32_t box[2] = {box_cols, box_rows};
    cuuint32_t estr[2] = {1, 1};
    return fn(map, CU_TENSOR_MAP_DATA_TYPE_BFLOAT16, 2, const_cast<void*>(ptr), dims, strides, box, estr,
              CU_TENSOR_MAP_INTERLEAVE_NONE, swz, promo, CU_TENSOR_MAP_FLOAT_OOB_FILL_NONE) == CUDA_SUCCESS;
}

}

extern "C" void kernel_launch(void* const* d_in, const int* in_sizes, int n_in, void* d_out, int out_size) {
    (void)in_sizes; (void)n_in; (void)out_size;
    const __nv_bfloat16* x = (const __nv_bfloat16*)d_in[0];
    const void* kc = d_in[1];
    const void* vc = d_in[2];
    const void* wq = d_in[3];
    const void* wo = d_in[4];

    static EncodeTiledFn encode = nullptr;
    static Scratch* scratch = nullptr;
    if (!encode) {
        void* fn = nullptr;
        cudaDriverEntryPointQueryResult qres;
        cudaGetDriverEntryPoint("cuTensorMapEncodeTiled", &fn, cudaEnableDefault, &qres);
        encode = (EncodeTiledFn)fn;
        cudaFuncSetAttribute(gqa_decode_kernel, cudaFuncAttributeMaxDynamicSharedMemorySize, kSmemTotal);
        void* sp = nullptr;
        cudaGetSymbolAddress(&sp, g_scratch);
        scratch = (Scratch*)sp;
    }
    CUtensorMap tmK, tmV, tmWq, tmWo;
    make_map(encode, &tmK, kc, kDH, (uint64_t)kB * kHKV * kSK, 64, kTile, CU_TENSOR_MAP_SWIZZLE_128B,
             CU_TENSOR_MAP_L2_PROMOTION_L2_256B);
    make_map(encode, &tmV, vc, kDH, (uint64_t)kB * kHKV * kSK, 64, kTile, CU_TENSOR_MAP_SWIZZLE_128B,
             CU_TENSOR_MAP_L2_PROMOTION_L2_256B);
    make_map(encode, &tmWq, wq, kHQ * kDH, kD, 32, 256, CU_TENSOR_MAP_SWIZZLE_64B, CU_TENSOR_MAP_L2_PROMOTION_L2_128B);
    make_map(encode, &tmWo, wo, kD, (uint64_t)kHQ * kDH, 64, kTile, CU_TENSOR_MAP_SWIZZLE_128B,
             CU_TENSOR_MAP_L2_PROMOTION_L2_256B);

    gqa_decode_kernel<<<kNCTA, kThreads, kSmemTotal>>>(tmK, tmV, tmWq, tmWo, x, (__nv_bfloat16*)d_out, scratch);
}
```

```cpp
#include <cuda_runtime.h>
#include <cuda_bf16.h>
#include <cuda.h>
#include <stdint.h>

namespace {

constexpr int kB = 8, kD = 512, kHQ = 32, kHKV = 8, kSK = 4096, kDH = 128;
constexpr int kNCTA = 64;
constexpr int kTile = 128;
constexpr int kNTiles = kSK / kTile;
constexpr int kStageBytes = kTile * kDH * 2;
constexpr int kNStage = 6;
constexpr int kNLoads = 2 + 2 * kNTiles + 2;
constexpr int kConsWarps = 8;
constexpr int kConsThreads = kConsWarps * 32;
constexpr int kThreads = kConsThreads + 32;
constexpr int kPosV30 = kNLoads - 4, kPosV31 = kNLoads - 3, kPosWo0 = kNLoads - 2, kPosWo1 = kNLoads - 1;
constexpr int kWInit = 4, kWMin = 3, kWMax = 5;
constexpr int kSchedNs = 640;
constexpr int kWoKs = 4;
constexpr int kWoP = 8 / kWoKs;

constexpr int kSmemStages = 0;
constexpr int kSmemScr = kNStage * kStageBytes;
constexpr int kScrRed  = kSmemScr;
constexpr int kScrPart = kSmemScr;
constexpr int kScrX    = kSmemScr + 8 * 8 * 68 * 4;
constexpr int kScrM    = kScrX;
constexpr int kScrPb   = kScrM + 4 * 8 * 4 * 4;
constexpr int kScrQs   = kScrX + kB * kD * 2;
constexpr int kScrOb   = kScrQs + 4 * 68 * 4;
constexpr int kSmemBars = kScrOb + 8 * 68 * 8;
constexpr int kSmemTotal = kSmemBars + 8 * (2 * kNStage + 3 + 2 * kWoP);
static_assert(kScrPb + 2 * 8 * 32 * 8 <= kScrQs, "scratch overlap");
static_assert(8 * 4 * 136 * 4 == 8 * 8 * 68 * 4, "red / part");
static_assert(kSmemTotal <= 232448, "smem budget");
static_assert(kScrOb % 8 == 0 && kSmemBars % 8 == 0, "alignment");

constexpr float kScaleLog2 = 0.08838834764831845f * 1.4426950408889634f;

struct __align__(128) Scratch {
    uint4 p[kNCTA * 16 * 16];
    uint32_t epoch[kNCTA * 32];
};
__device__ Scratch g_scratch;

__device__ __forceinline__ uint32_t smem_u32(const void* p) {
    return (uint32_t)__cvta_generic_to_shared(p);
}
__device__ __forceinline__ void mbar_init(uint32_t bar, uint32_t count) {
    asm volatile("mbarrier.init.shared::cta.b64 [%0], %1;" ::"r"(bar), "r"(count) : "memory");
}
__device__ __forceinline__ void mbar_expect_tx(uint32_t bar, uint32_t bytes) {
    asm volatile("mbarrier.arrive.expect_tx.shared::cta.b64 _, [%0], %1;" ::"r"(bar), "r"(bytes) : "memory");
}
__device__ __forceinline__ void mbar_arrive(uint32_t bar) {
    asm volatile("mbarrier.arrive.shared::cta.b64 _, [%0];" ::"r"(bar) : "memory");
}
__device__ __forceinline__ bool mbar_try_wait(uint32_t bar, uint32_t parity) {
    uint32_t ok;
    asm volatile(
        "{\n\t.reg .pred p;\n\t"
        "mbarrier.try_wait.parity.shared::cta.b64 p, [%1], %2;\n\t"
        "selp.u32 %0, 1, 0, p;\n\t}"
        : "=r"(ok) : "r"(bar), "r"(parity) : "memory");
    return ok != 0;
}
__device__ __forceinline__ bool mbar_test_wait(uint32_t bar, uint32_t parity) {
    uint32_t ok;
    asm volatile(
        "{\n\t.reg .pred p;\n\t"
        "mbarrier.test_wait.parity.shared::cta.b64 p, [%1], %2;\n\t"
        "selp.u32 %0, 1, 0, p;\n\t}"
        : "=r"(ok) : "r"(bar), "r"(parity) : "memory");
    return ok != 0;
}
__device__ __forceinline__ void mbar_wait(uint32_t bar, uint32_t parity) {
    uint32_t spins = 0;
    while (!mbar_try_wait(bar, parity)) {
        if (++spins > (1u << 24)) __trap();
    }
}
__device__ __forceinline__ uint32_t mapa(uint32_t addr, uint32_t rank) {
    uint32_t r;
    asm("mapa.shared::cluster.u32 %0, %1, %2;" : "=r"(r) : "r"(addr), "r"(rank));
    return r;
}
__device__ __forceinline__ void st_async32(uint32_t addr, uint32_t v, uint32_t bar) {
    asm volatile("st.async.weak.shared::cluster.mbarrier::complete_tx::bytes.b32 [%0], %1, [%2];"
                 ::"r"(addr), "r"(v), "r"(bar) : "memory");
}
__device__ __forceinline__ void st_async64(uint32_t addr, uint32_t lo, uint32_t hi, uint32_t bar) {
    asm volatile("st.async.weak.shared::cluster.mbarrier::complete_tx::bytes.v2.b32 [%0], {%1, %2}, [%3];"
                 ::"r"(addr), "r"(lo), "r"(hi), "r"(bar) : "memory");
}
__device__ __forceinline__ void cluster_arrive() {
    asm volatile("barrier.cluster.arrive.relaxed.aligned;" ::: "memory");
}
__device__ __forceinline__ void cluster_wait() {
    asm volatile("barrier.cluster.wait.acquire.aligned;" ::: "memory");
}
__device__ __forceinline__ void tma_load_2d(uint32_t dst, const CUtensorMap* map, int c0, int c1,
                                            uint32_t bar, uint64_t policy) {
    asm volatile(
        "cp.async.bulk.tensor.2d.shared::cluster.global.mbarrier::complete_tx::bytes.L2::cache_hint "
        "[%0], [%1, {%3, %4}], [%2], %5;"
        ::"r"(dst), "l"(map), "r"(bar), "r"(c0), "r"(c1), "l"(policy) : "memory");
}
__device__ __forceinline__ void tma_load_4d(uint32_t dst, const CUtensorMap* map, int c0, int c3,
                                            uint32_t bar, uint64_t policy) {
    asm volatile(
        "cp.async.bulk.tensor.4d.shared::cluster.global.mbarrier::complete_tx::bytes.L2::cache_hint "
        "[%0], [%1, {%3, %4, %4, %5}], [%2], %6;"
        ::"r"(dst), "l"(map), "r"(bar), "r"(c0), "r"(0), "r"(c3), "l"(policy) : "memory");
}
__device__ __forceinline__ uint2 lds64(uint32_t addr) {
    uint2 v;
    asm volatile("ld.shared.v2.u32 {%0, %1}, [%2];" : "=r"(v.x), "=r"(v.y) : "r"(addr) : "memory");
    return v;
}
__device__ __forceinline__ void cons_bar() { asm volatile("bar.sync 1, 256;" ::: "memory"); }

__device__ __forceinline__ void ldsm_x4(uint32_t addr, uint32_t& r0, uint32_t& r1, uint32_t& r2, uint32_t& r3) {
    asm volatile("ldmatrix.sync.aligned.m8n8.x4.shared.b16 {%0,%1,%2,%3}, [%4];"
                 : "=r"(r0), "=r"(r1), "=r"(r2), "=r"(r3) : "r"(addr) : "memory");
}
__device__ __forceinline__ void ldsm_x4_t(uint32_t addr, uint32_t& r0, uint32_t& r1, uint32_t& r2, uint32_t& r3) {
    asm volatile("ldmatrix.sync.aligned.m8n8.x4.trans.shared.b16 {%0,%1,%2,%3}, [%4];"
                 : "=r"(r0), "=r"(r1), "=r"(r2), "=r"(r3) : "r"(addr) : "memory");
}
__device__ __forceinline__ void mma_bf16(float (&c)[4], uint32_t a0, uint32_t a1, uint32_t a2, uint32_t a3,
                                         uint32_t b0, uint32_t b1) {
    asm volatile(
        "mma.sync.aligned.m16n8k16.row.col.f32.bf16.bf16.f32 {%0,%1,%2,%3}, {%4,%5,%6,%7}, {%8,%9}, {%0,%1,%2,%3};"
        : "+f"(c[0]), "+f"(c[1]), "+f"(c[2]), "+f"(c[3])
        : "r"(a0), "r"(a1), "r"(a2), "r"(a3), "r"(b0), "r"(b1));
}
__device__ __forceinline__ uint32_t movmatrix_t(uint32_t a) {
    uint32_t d;
    asm volatile("movmatrix.sync.aligned.m8n8.trans.b16 %0, %1;" : "=r"(d) : "r"(a));
    return d;
}
__device__ __forceinline__ uint32_t pack_bf16(float lo, float hi) {
    uint32_t d;
    asm("cvt.rn.bf16x2.f32 %0, %1, %2;" : "=r"(d) : "f"(hi), "f"(lo));
    return d;
}
__device__ __forceinline__ float ex2(float x) {
    float y;
    asm("ex2.approx.ftz.f32 %0, %1;" : "=f"(y) : "f"(x));
    return y;
}
__device__ __forceinline__ float rcp(float x) {
    float y;
    asm("rcp.approx.ftz.f32 %0, %1;" : "=f"(y) : "f"(x));
    return y;
}
__device__ __forceinline__ uint32_t gtimer_lo() {
    uint32_t t;
    asm volatile("mov.u32 %0, %globaltimer_lo;" : "=r"(t));
    return t;
}
__device__ __forceinline__ void st_relaxed4(void* p, uint32_t a, uint32_t b, uint32_t c, uint32_t d) {
    asm volatile("st.relaxed.gpu.global.v4.u32 [%0], {%1, %2, %3, %4};" ::"l"(p), "r"(a), "r"(b), "r"(c), "r"(d) : "memory");
}
__device__ __forceinline__ uint4 ld_relaxed4(const void* p) {
    uint4 v;
    asm volatile("ld.relaxed.gpu.global.v4.u32 {%0, %1, %2, %3}, [%4];"
                 : "=r"(v.x), "=r"(v.y), "=r"(v.z), "=r"(v.w) : "l"(p) : "memory");
    return v;
}
template <typename T> __device__ __forceinline__ void pin64(T*& p) {
    asm volatile("" : "+l"(p));
}
__device__ __forceinline__ void pin32(uint32_t& v) {
    asm volatile("" : "+r"(v));
}

constexpr uint32_t kSpinLimit = 1u << 22;

__global__ void __cluster_dims__(8, 1, 1) __launch_bounds__(kThreads, 1)
gqa_decode_kernel(const __grid_constant__ CUtensorMap tmK, const __grid_constant__ CUtensorMap tmV,
                  const __grid_constant__ CUtensorMap tmWq, const __grid_constant__ CUtensorMap tmWo,
                  const __nv_bfloat16* __restrict__ x,
                  const __nv_bfloat16* __restrict__ wq, __nv_bfloat16* __restrict__ out,
                  Scratch* __restrict__ scr) {
    extern __shared__ __align__(1024) uint8_t smem[];
    const uint32_t sbase = smem_u32(smem);
    const int tid = threadIdx.x;
    const int warp = tid >> 5, lane = tid & 31;
    const int cta = blockIdx.x;
    const int hkv = cta >> 3;
    const int rank = cta & 7;
    const int kh = rank & 1;
    const int cg = rank >> 1;
    const uint32_t bar_full = sbase + kSmemBars;
    const uint32_t bar_empty = bar_full + 8 * kNStage;
    const uint32_t bar_x = bar_empty + 8 * kNStage;
    const uint32_t bar_q = bar_x + 8;
    const uint32_t bar_o = bar_q + 8;
    const uint32_t bar_wo = bar_o + 8;
    const int row0 = (rank * kHKV + hkv) * kSK;

    if (tid == 0) {
        asm volatile("cp.async.bulk.prefetch.L2.global [%0], %1;" ::"l"(wq + (size_t)cta * 32768), "n"(32768) : "memory");
        asm volatile("cp.async.bulk.prefetch.L2.global [%0], %1;" ::"l"(wq + (size_t)cta * 32768 + 16384), "n"(32768) : "memory");
    }

    if (warp == kConsWarps) {
        if (lane == 0) {
#pragma unroll
            for (int s = 0; s < kNStage; s++) {
                mbar_init(bar_full + 8 * s, 1);
                mbar_init(bar_empty + 8 * s, kConsWarps);
            }
            mbar_init(bar_x, 1);
            mbar_init(bar_q, 1);
            mbar_init(bar_o, 1);
#pragma unroll
            for (int s = 0; s < 2 * (kWoP - 1); s++) mbar_init(bar_wo + 8 * s, 1);
            mbar_expect_tx(bar_q, 4 * 64 * 4);
            mbar_expect_tx(bar_o, 8 * 64 * 8);
            asm volatile("fence.mbarrier_init.release.cluster;" ::: "memory");
            asm volatile("fence.proxy.async.shared::cta;" ::: "memory");
            mbar_expect_tx(bar_x, kB * kD * 2);
            asm volatile("cp.async.bulk.shared::cluster.global.mbarrier::complete_tx::bytes [%0], [%1], %2, [%3];"
                         ::"r"(sbase + kScrX), "l"(x), "n"(kB * kD * 2), "r"(bar_x) : "memory");
        }
        const uint32_t tstart = gtimer_lo();
        uint64_t policy;
        asm volatile("createpolicy.fractional.L2::evict_first.b64 %0, 1.0;" : "=l"(policy));
        auto issue = [&](int i, int s) {
            const uint32_t dst = sbase + kSmemStages + s * kStageBytes;
            const uint32_t bar = bar_full + 8 * s;
            if (i == kPosWo0 || i == kPosWo1) {
                const int hs = (i == kPosWo1 ? 1 : 0);
                const int h = hkv * 4 + kh * 2 + hs;
#pragma unroll
                for (int p = 0; p < kWoP; p++) {
                    const uint32_t pb = (p == kWoP - 1) ? bar : bar_wo + 8 * (hs * (kWoP - 1) + p);
                    mbar_expect_tx(pb, kStageBytes / kWoP);
                    tma_load_4d(dst + p * kWoKs * 2048, &tmWo, cg * 128, h * 8 + p * kWoKs, pb, policy);
                    tma_load_4d(dst + 16384 + p * kWoKs * 2048, &tmWo, cg * 128 + 64, h * 8 + p * kWoKs, pb, policy);
                }
                return;
            }
            mbar_expect_tx(bar, kStageBytes);
            if (i < 2) {
                tma_load_2d(dst, &tmWq, hkv * 512 + rank * 64, i * 256, bar, policy);
            } else {
                const int kv = i - 2;
                const bool isv = (kv < 2 * kNTiles - 4) ? (kv & 1) : (kv >= 2 * kNTiles - 2);
                const int tl = (kv < 2 * kNTiles - 4) ? (kv >> 1) : (kv < 2 * kNTiles - 2) ? kNTiles - 2 + (kv & 1)
                                                                   : (i == kPosV30 ? kNTiles - 2 : kNTiles - 1);
                const CUtensorMap* map = isv ? &tmV : &tmK;
                const int row = row0 + tl * kTile;
                tma_load_2d(dst, map, 0, row, bar, policy);
                tma_load_2d(dst + 16384, map, 64, row, bar, policy);
            }
        };
        if (lane == 0) {
#pragma unroll
            for (int i = 0; i < kWInit; i++) issue(i, i);
        }
        __syncthreads();
        cluster_arrive();
        cluster_wait();
        if (lane == 0) {
            int s = kWInit, ph = 1;
            int ws = 0, wph = 0, done = 0;
            uint32_t due = tstart + (uint32_t)(kWInit * kSchedNs);
            for (int i = kWInit; i < kNLoads; i++) {
                mbar_wait(bar_empty + 8 * s, ph);
                uint32_t spins = 0;
                while (true) {
                    if (done < i && mbar_test_wait(bar_full + 8 * ws, wph)) {
                        done++;
                        if (++ws == kNStage) { ws = 0; wph ^= 1; }
                    }
                    const int infl = i - done;
                    if (i == kPosWo0) {
                        if (infl <= 1) break;
                        if (++spins > (1u << 26)) __trap();
                        continue;
                    }
                    if (infl < kWMin) break;
                    if (infl < kWMax && (int)(gtimer_lo() - due) >= 0) break;
                    if (++spins > (1u << 26)) __trap();
                }
                issue(i, s);
                due += kSchedNs;
                if (++s == kNStage) { s = 0; ph ^= 1; }
            }
        }
        return;
    }

    const int g = lane >> 2, j = lane & 3;
    const int jj = j & 1;

    uint32_t tag = __ldcg(&scr->epoch[cta * 32]);
    uint4* p_dst = &scr->p[((j * 16 + cg * 4 + (warp >> 1)) * 16 + hkv * 2 + kh) * 16 + (warp & 1) * 8 + g];
    __syncthreads();
    cluster_arrive();
    uint32_t xb[4][2];
    {
        mbar_wait(bar_x, 0);
        const uint32_t* xs = reinterpret_cast<const uint32_t*>(smem + kScrX) + g * 256 + warp * 32 + j;
#pragma unroll
        for (int s = 0; s < 4; s++) { xb[s][0] = xs[s * 8]; xb[s][1] = xs[s * 8 + 4]; }
    }
    st_relaxed4(p_dst, tag & 15u, tag & 15u, tag & 15u, tag & 15u);
    tag += 1;
    {
        float qa[4][4];
#pragma unroll
        for (int mt = 0; mt < 4; mt++) { qa[mt][0] = qa[mt][1] = qa[mt][2] = qa[mt][3] = 0.f; }
        mbar_wait(bar_full + 8 * (warp >> 2), 0);
#pragma unroll
        for (int s = 0; s < 4; s++) {
            const int row = (warp & 3) * 64 + s * 16 + (lane & 7) + ((lane >> 4) << 3);
#pragma unroll
            for (int mt = 0; mt < 4; mt++) {
                const int c = 2 * mt + ((lane >> 3) & 1);
                uint32_t a0, a1, a2, a3;
                ldsm_x4_t(sbase + kSmemStages + (warp >> 2) * kStageBytes + row * 128 + ((c ^ (row & 7)) << 4), a0, a1, a2, a3);
                mma_bf16(qa[mt], a0, a1, a2, a3, xb[s][0], xb[s][1]);
            }
        }
        __syncwarp();
        if (lane == 0) { mbar_arrive(bar_empty); mbar_arrive(bar_empty + 8); }
        float* red = reinterpret_cast<float*>(smem + kScrRed) + warp * (8 * 68);
#pragma unroll
        for (int mt = 0; mt < 4; mt++) {
            red[(2 * j) * 68 + mt * 16 + g] = qa[mt][0];
            red[(2 * j + 1) * 68 + mt * 16 + g] = qa[mt][1];
            red[(2 * j) * 68 + mt * 16 + g + 8] = qa[mt][2];
            red[(2 * j + 1) * 68 + mt * 16 + g + 8] = qa[mt][3];
        }
    }
    cons_bar();
    cluster_wait();
    {
        const float* red = reinterpret_cast<const float*>(smem + kScrRed) + warp * 68 + 2 * lane;
        float s0 = 0.f, s1 = 0.f;
#pragma unroll
        for (int w = 0; w < 8; w++) {
            const float2 v = *reinterpret_cast<const float2*>(red + w * (8 * 68));
            s0 += v.x; s1 += v.y;
        }
        st_async32(mapa(sbase + kScrQs + ((rank >> 1) * 68 + (rank & 1) * 32 + lane) * 4, warp), pack_bf16(s0, s1),
                   mapa(bar_q, warp));
    }
    uint32_t qb[8][2];
    {
        mbar_wait(bar_q, 0);
        const uint32_t* qs = reinterpret_cast<const uint32_t*>(smem + kScrQs) + (g & 3) * 68 + j;
#pragma unroll
        for (int s = 0; s < 8; s++) { qb[s][0] = qs[8 * s]; qb[s][1] = qs[8 * s + 4]; }
    }

    float oacc[8][4];
#pragma unroll
    for (int t = 0; t < 8; t++) { oacc[t][0] = oacc[t][1] = oacc[t][2] = oacc[t][3] = 0.f; }
    float lacc[4] = {0.f, 0.f, 0.f, 0.f};
    float m0 = -INFINITY, m1 = -INFINITY;

    uint32_t koff[4], voff[4];
    {
        const uint32_t krow = warp * 16 + (lane & 15);
        const uint32_t ky = ((lane >> 4) ^ (lane & 7)) << 4;
        const uint32_t vrow = warp * 16 + (lane & 7) + ((lane >> 4) << 3);
        const uint32_t vy = (((lane >> 3) & 1) ^ (lane & 7)) << 4;
#pragma unroll
        for (int s = 0; s < 4; s++) {
            koff[s] = krow * 128 + (ky ^ (s << 5));
            voff[s] = vrow * 128 + (vy ^ (s << 5));
        }
    }

    int stage = 2, phase = 0;
    auto qk = [&](float (&s)[4]) {
        float sc[2][4] = {{0.f, 0.f, 0.f, 0.f}, {0.f, 0.f, 0.f, 0.f}};
        mbar_wait(bar_full + 8 * stage, phase);
        const uint32_t kb = sbase + kSmemStages + stage * kStageBytes;
#pragma unroll
        for (int k = 0; k < 8; k++) {
            uint32_t a0, a1, a2, a3;
            ldsm_x4(kb + koff[k & 3] + (k >> 2) * 16384, a0, a1, a2, a3);
            mma_bf16(sc[k & 1], a0, a1, a2, a3, qb[k][0], qb[k][1]);
        }
        __syncwarp();
        if (lane == 0) mbar_arrive(bar_empty + 8 * stage);
        if (++stage == kNStage) { stage = 0; phase ^= 1; }
#pragma unroll
        for (int e = 0; e < 4; e++) s[e] = sc[0][e] + sc[1][e];
    };
#pragma unroll 1
    for (int t = 0; t < kNTiles - 2; t++) {
        float s[4];
        qk(s);
        float t0 = fmaxf(s[0], s[2]), t1 = fmaxf(s[1], s[3]);
#pragma unroll
        for (int o = 4; o < 32; o <<= 1) {
            t0 = fmaxf(t0, __shfl_xor_sync(0xffffffffu, t0, o));
            t1 = fmaxf(t1, __shfl_xor_sync(0xffffffffu, t1, o));
        }
        const float mn0 = fmaxf(m0, t0), mn1 = fmaxf(m1, t1);
        const float al0 = ex2((m0 - mn0) * kScaleLog2), al1 = ex2((m1 - mn1) * kScaleLog2);
        m0 = mn0; m1 = mn1;
        const float b0 = mn0 * kScaleLog2, b1 = mn1 * kScaleLog2;
        const float p0 = ex2(fmaf(s[0], kScaleLog2, -b0)), p1 = ex2(fmaf(s[1], kScaleLog2, -b1));
        const float p2 = ex2(fmaf(s[2], kScaleLog2, -b0)), p3 = ex2(fmaf(s[3], kScaleLog2, -b1));
        const uint32_t pb0 = movmatrix_t(pack_bf16(p0, p1));
        const uint32_t pb1 = movmatrix_t(pack_bf16(p2, p3));
#pragma unroll
        for (int mt = 0; mt < 8; mt++) {
            oacc[mt][0] *= al0; oacc[mt][1] *= al1; oacc[mt][2] *= al0; oacc[mt][3] *= al1;
        }
        lacc[0] *= al0; lacc[1] *= al1;
        mma_bf16(lacc, 0x3f803f80u, 0x3f803f80u, 0x3f803f80u, 0x3f803f80u, pb0, pb1);
        {
            mbar_wait(bar_full + 8 * stage, phase);
            const uint32_t vb = sbase + kSmemStages + stage * kStageBytes;
#pragma unroll
            for (int mt = 0; mt < 8; mt++) {
                uint32_t a0, a1, a2, a3;
                ldsm_x4_t(vb + voff[mt & 3] + (mt >> 2) * 16384, a0, a1, a2, a3);
                mma_bf16(oacc[mt], a0, a1, a2, a3, pb0, pb1);
            }
            __syncwarp();
            if (lane == 0) mbar_arrive(bar_empty + 8 * stage);
            if (++stage == kNStage) { stage = 0; phase ^= 1; }
        }
    }
    constexpr int kVaStage = kPosV30 % kNStage, kVaPhase = (kPosV30 / kNStage) & 1;
    constexpr int kVStage = kPosV31 % kNStage, kVPhase = (kPosV31 / kNStage) & 1;
    constexpr int kWo0Stage = kPosWo0 % kNStage, kWo0Phase = (kPosWo0 / kNStage) & 1;
    constexpr int kWo1Stage = kPosWo1 % kNStage, kWo1Phase = (kPosWo1 / kNStage) & 1;

    float2* mx = reinterpret_cast<float2*>(smem + kScrM);
    float c[4][4];
    float M0, M1, L0 = 0.f, L1 = 0.f;
    {
        if (lane < 2) mx[warp * 2 + lane] = make_float2(m0, m1);
        cons_bar();
        M0 = -INFINITY; M1 = -INFINITY;
#pragma unroll
        for (int w = 0; w < 8; w++) {
            const float2 v = mx[w * 2 + jj];
            M0 = fmaxf(M0, v.x); M1 = fmaxf(M1, v.y);
        }
        const float f0 = ex2((m0 - M0) * kScaleLog2), f1 = ex2((m1 - M1) * kScaleLog2);
        float* part = reinterpret_cast<float*>(smem + kScrPart) + warp * (4 * 136) + (2 * jj) * 136 + (j >> 1) * 72 + g;
#pragma unroll
        for (int mt = 0; mt < 4; mt++) {
            part[mt * 16] = (j < 2 ? oacc[mt][0] : oacc[mt + 4][0]) * f0;
            part[136 + mt * 16] = (j < 2 ? oacc[mt][1] : oacc[mt + 4][1]) * f1;
            part[mt * 16 + 8] = (j < 2 ? oacc[mt][2] : oacc[mt + 4][2]) * f0;
            part[136 + mt * 16 + 8] = (j < 2 ? oacc[mt][3] : oacc[mt + 4][3]) * f1;
        }
        if (lane < 2) mx[16 + warp * 2 + lane] = make_float2(lacc[0] * f0, lacc[1] * f1);
        cons_bar();
        const float* pr = reinterpret_cast<const float*>(smem + kScrPart) + (2 * jj) * 136 + warp * 16 + (warp >> 2) * 8 + g;
#pragma unroll
        for (int i = 0; i < 4; i++) { c[i][0] = c[i][1] = c[i][2] = c[i][3] = 0.f; }
#pragma unroll
        for (int w = 0; w < 8; w++) {
            const float* pw = pr + w * (4 * 136);
            c[0][0] += pw[0]; c[0][1] += pw[136]; c[0][2] += pw[8]; c[0][3] += pw[136 + 8];
            const float2 v = mx[16 + w * 2 + jj];
            L0 += v.x; L1 += v.y;
        }
    }

    uint32_t o_dst0 = mapa(sbase + kScrOb + (rank * 68 + warp * 8 + g) * 8, (j >> 1) * 4 + jj);
    uint32_t o_dst1 = mapa(sbase + kScrOb + (rank * 68 + warp * 8 + g) * 8, (j >> 1) * 4 + 2 + jj);
    uint32_t o_bar0 = mapa(bar_o, (j >> 1) * 4 + jj);
    uint32_t o_bar1 = mapa(bar_o, (j >> 1) * 4 + 2 + jj);
    const uint4* p_src = &scr->p[cta * 256 + tid];
    const int opos = tid & 63;
    __nv_bfloat16* out_dst = out + (2 * (cta >> 4) + (opos & 1)) * kD + (cta & 15) * 32 + (opos >> 5) * 16 +
                             ((opos >> 2) & 7) + ((opos >> 1) & 1) * 8;
    uint32_t* epoch_dst = &scr->epoch[cta * 32];
    const uint32_t vrel = (warp >> 2) * 16384 + ((lane & 7) + ((lane >> 4) << 3)) * 128 +
                          (((((2 * warp) & 7) + ((lane >> 3) & 1)) ^ (lane & 7)) << 4);
    uint32_t vb = sbase + kSmemStages + kVStage * kStageBytes + vrel;
    uint32_t va = sbase + kSmemStages + kVaStage * kStageBytes + vrel;
    uint32_t wb0 = sbase + kSmemStages + kWo0Stage * kStageBytes + vrel;
    uint32_t wb1 = sbase + kSmemStages + kWo1Stage * kStageBytes + vrel;
    uint32_t obp = sbase + kScrOb + (g * 68 + j) * 8;
    pin32(o_dst0); pin32(o_dst1); pin32(o_bar0); pin32(o_bar1); pin32(vb); pin32(va); pin32(wb0); pin32(wb1); pin32(obp);
    pin64(p_dst); pin64(p_src); pin64(out_dst); pin64(epoch_dst);

    {
        float sa[4], sb[4];
        qk(sa);
        qk(sb);
        float t0 = fmaxf(fmaxf(sa[0], sa[2]), fmaxf(sb[0], sb[2])), t1 = fmaxf(fmaxf(sa[1], sa[3]), fmaxf(sb[1], sb[3]));
#pragma unroll
        for (int o = 4; o < 32; o <<= 1) {
            t0 = fmaxf(t0, __shfl_xor_sync(0xffffffffu, t0, o));
            t1 = fmaxf(t1, __shfl_xor_sync(0xffffffffu, t1, o));
        }
        if (lane < 2) mx[32 + warp * 2 + lane] = make_float2(t0, t1);
        cons_bar();
        float N0 = M0, N1 = M1;
#pragma unroll
        for (int w = 0; w < 8; w++) {
            const float2 v = mx[32 + w * 2 + jj];
            N0 = fmaxf(N0, v.x); N1 = fmaxf(N1, v.y);
        }
        const float b0 = N0 * kScaleLog2, b1 = N1 * kScaleLog2;
        const uint32_t pa0 = movmatrix_t(pack_bf16(ex2(fmaf(sa[0], kScaleLog2, -b0)), ex2(fmaf(sa[1], kScaleLog2, -b1))));
        const uint32_t pa1 = movmatrix_t(pack_bf16(ex2(fmaf(sa[2], kScaleLog2, -b0)), ex2(fmaf(sa[3], kScaleLog2, -b1))));
        const uint32_t pl0 = movmatrix_t(pack_bf16(ex2(fmaf(sb[0], kScaleLog2, -b0)), ex2(fmaf(sb[1], kScaleLog2, -b1))));
        const uint32_t pl1 = movmatrix_t(pack_bf16(ex2(fmaf(sb[2], kScaleLog2, -b0)), ex2(fmaf(sb[3], kScaleLog2, -b1))));
        reinterpret_cast<uint2*>(smem + kScrPb)[warp * 32 + lane] = make_uint2(pa0, pa1);
        reinterpret_cast<uint2*>(smem + kScrPb)[256 + warp * 32 + lane] = make_uint2(pl0, pl1);
        float la[4] = {0.f, 0.f, 0.f, 0.f}, lb[4] = {0.f, 0.f, 0.f, 0.f};
        mma_bf16(la, 0x3f803f80u, 0x3f803f80u, 0x3f803f80u, 0x3f803f80u, pa0, pa1);
        mma_bf16(lb, 0x3f803f80u, 0x3f803f80u, 0x3f803f80u, 0x3f803f80u, pl0, pl1);
        if (lane < 2) mx[48 + warp * 2 + lane] = make_float2(la[0] + lb[0], la[1] + lb[1]);
        const float al0 = ex2((M0 - N0) * kScaleLog2), al1 = ex2((M1 - N1) * kScaleLog2);
        c[0][0] *= al0; c[0][1] *= al1; c[0][2] *= al0; c[0][3] *= al1;
        L0 *= al0; L1 *= al1;
        cons_bar();
        uint2 pf[8], pg[8];
#pragma unroll
        for (int w = 0; w < 8; w++) {
            pg[w] = reinterpret_cast<const uint2*>(smem + kScrPb)[w * 32 + lane];
            pf[w] = reinterpret_cast<const uint2*>(smem + kScrPb)[256 + w * 32 + lane];
            const float2 v = mx[48 + w * 2 + jj];
            L0 += v.x; L1 += v.y;
        }
        const float inv0 = rcp(L0), inv1 = rcp(L1);
        mbar_wait(bar_full + 8 * kVaStage, kVaPhase);
#pragma unroll
        for (int w = 0; w < 8; w++) {
            uint32_t a0, a1, a2, a3;
            ldsm_x4_t(va + w * 16 * 128, a0, a1, a2, a3);
            mma_bf16(c[w & 3], a0, a1, a2, a3, pg[w].x, pg[w].y);
        }
        mbar_wait(bar_full + 8 * kVStage, kVPhase);
#pragma unroll
        for (int w = 0; w < 8; w++) {
            uint32_t a0, a1, a2, a3;
            ldsm_x4_t(vb + w * 16 * 128, a0, a1, a2, a3);
            mma_bf16(c[w & 3], a0, a1, a2, a3, pf[w].x, pf[w].y);
        }
        float z[4];
#pragma unroll
        for (int e = 0; e < 4; e++) z[e] = (c[0][e] + c[1][e]) + (c[2][e] + c[3][e]);
        const uint32_t w0 = pack_bf16(z[0] * inv0, z[2] * inv0), w1 = pack_bf16(z[1] * inv1, z[3] * inv1);
        st_async64(o_dst0, w0, w1, o_bar0);
        st_async64(o_dst1, w0, w1, o_bar1);
    }

    {
        auto piece_bar = [&](int hs, int p) -> uint32_t {
            return (p == kWoP - 1) ? bar_full + 8 * (hs ? kWo1Stage : kWo0Stage) : bar_wo + 8 * (hs * (kWoP - 1) + p);
        };
        auto piece_par = [&](int hs, int p) -> uint32_t { return (p == kWoP - 1) ? (hs ? kWo1Phase : kWo0Phase) : 0; };
        auto landed = [&](int hs) -> bool {
            bool ok = true;
#pragma unroll
            for (int p = 0; p < kWoP; p++) ok = ok && mbar_test_wait(piece_bar(hs, p), piece_par(hs, p));
            return ok;
        };
        uint32_t wa[16][4];
        bool have_a = false, have_b = false;
        {
            uint32_t spins = 0;
            while (!__all_sync(0xffffffffu, mbar_test_wait(bar_o, 0))) {
                if (!have_a) {
                    if (__all_sync(0xffffffffu, landed(0))) {
#pragma unroll
                        for (int s = 0; s < 8; s++) ldsm_x4_t(wb0 + s * 2048, wa[s][0], wa[s][1], wa[s][2], wa[s][3]);
                        have_a = true;
                    }
                } else if (!have_b) {
                    if (__all_sync(0xffffffffu, landed(1))) {
#pragma unroll
                        for (int s = 0; s < 8; s++) ldsm_x4_t(wb1 + s * 2048, wa[8 + s][0], wa[8 + s][1], wa[8 + s][2], wa[8 + s][3]);
                        have_b = true;
                    }
                }
                if (++spins > (1u << 24)) __trap();
            }
        }
        uint2 b0[8], b1[8];
#pragma unroll
        for (int s = 0; s < 8; s++) { b0[s] = lds64(obp + 64 * s); b1[s] = lds64(obp + 64 * s + 32); }
        float c[4][4];
#pragma unroll
        for (int i = 0; i < 4; i++) { c[i][0] = c[i][1] = c[i][2] = c[i][3] = 0.f; }
        if (have_a) {
#pragma unroll
            for (int s = 0; s < 8; s++) mma_bf16(c[s & 3], wa[s][0], wa[s][1], wa[s][2], wa[s][3], b0[s].x, b1[s].x);
        } else {
#pragma unroll
            for (int p = 0; p < kWoP; p++) {
                mbar_wait(piece_bar(0, p), piece_par(0, p));
#pragma unroll
                for (int s = p * kWoKs; s < (p + 1) * kWoKs; s++) {
                    uint32_t a0, a1, a2, a3;
                    ldsm_x4_t(wb0 + s * 2048, a0, a1, a2, a3);
                    mma_bf16(c[s & 3], a0, a1, a2, a3, b0[s].x, b1[s].x);
                }
            }
        }
        if (have_b) {
#pragma unroll
            for (int s = 0; s < 8; s++) mma_bf16(c[s & 3], wa[8 + s][0], wa[8 + s][1], wa[8 + s][2], wa[8 + s][3], b0[s].y, b1[s].y);
        } else {
#pragma unroll
            for (int p = 0; p < kWoP; p++) {
                mbar_wait(piece_bar(1, p), piece_par(1, p));
#pragma unroll
                for (int s = p * kWoKs; s < (p + 1) * kWoKs; s++) {
                    uint32_t a0, a1, a2, a3;
                    ldsm_x4_t(wb1 + s * 2048, a0, a1, a2, a3);
                    mma_bf16(c[s & 3], a0, a1, a2, a3, b0[s].y, b1[s].y);
                }
            }
        }
        float v[4];
#pragma unroll
        for (int e = 0; e < 4; e++) v[e] = (c[0][e] + c[1][e]) + (c[2][e] + c[3][e]);
        const uint32_t t4 = tag & 15u;
        st_relaxed4(p_dst, (__float_as_uint(v[0]) & ~15u) | t4, (__float_as_uint(v[1]) & ~15u) | t4,
                    (__float_as_uint(v[2]) & ~15u) | t4, (__float_as_uint(v[3]) & ~15u) | t4);
    }

    {
        const uint32_t t4 = tag & 15u;
        uint4 r;
        uint32_t spins = 0;
        while (true) {
            r = ld_relaxed4(p_src);
            const uint32_t bad = ((r.x ^ t4) | (r.y ^ t4) | (r.z ^ t4) | (r.w ^ t4)) & 15u;
            if (__all_sync(0xffffffffu, bad == 0)) break;
            if (++spins > kSpinLimit) __trap();
        }
        float* fr = reinterpret_cast<float*>(smem + kScrPart);
        *reinterpret_cast<uint4*>(fr + tid * 4) = make_uint4(r.x & ~15u, r.y & ~15u, r.z & ~15u, r.w & ~15u);
        cons_bar();
        if (warp < 2) {
            float z[16];
#pragma unroll
            for (int w = 0; w < 16; w++) z[w] = fr[w * 64 + opos];
            const float y0 = ((z[0] + z[1]) + (z[2] + z[3])) + ((z[4] + z[5]) + (z[6] + z[7]));
            const float y1 = ((z[8] + z[9]) + (z[10] + z[11])) + ((z[12] + z[13]) + (z[14] + z[15]));
            *out_dst = __float2bfloat16(y0 + y1);
            if (tid == 0) *epoch_dst = tag;
        }
    }
}

typedef CUresult (*EncodeTiledFn)(CUtensorMap*, CUtensorMapDataType, cuuint32_t, void*, const cuuint64_t*,
                                  const cuuint64_t*, const cuuint32_t*, const cuuint32_t*, CUtensorMapInterleave,
                                  CUtensorMapSwizzle, CUtensorMapL2promotion, CUtensorMapFloatOOBfill);

bool make_map(EncodeTiledFn fn, CUtensorMap* map, const void* ptr, uint64_t cols, uint64_t rows, uint32_t box_cols,
              uint32_t box_rows, CUtensorMapSwizzle swz, CUtensorMapL2promotion promo) {
    cuuint64_t dims[2] = {(cuuint64_t)cols, (cuuint64_t)rows};
    cuuint64_t strides[1] = {(cuuint64_t)cols * 2};
    cuuint32_t box[2] = {box_cols, box_rows};
    cuuint32_t estr[2] = {1, 1};
    return fn(map, CU_TENSOR_MAP_DATA_TYPE_BFLOAT16, 2, const_cast<void*>(ptr), dims, strides, box, estr,
              CU_TENSOR_MAP_INTERLEAVE_NONE, swz, promo, CU_TENSOR_MAP_FLOAT_OOB_FILL_NONE) == CUDA_SUCCESS;
}

}

extern "C" void kernel_launch(void* const* d_in, const int* in_sizes, int n_in, void* d_out, int out_size) {
    (void)in_sizes; (void)n_in; (void)out_size;
    const __nv_bfloat16* x = (const __nv_bfloat16*)d_in[0];
    const void* kc = d_in[1];
    const void* vc = d_in[2];
    const void* wq = d_in[3];
    const void* wo = d_in[4];

    static EncodeTiledFn encode = nullptr;
    static Scratch* scratch = nullptr;
    if (!encode) {
        void* fn = nullptr;
        cudaDriverEntryPointQueryResult qres;
        cudaGetDriverEntryPoint("cuTensorMapEncodeTiled", &fn, cudaEnableDefault, &qres);
        encode = (EncodeTiledFn)fn;
        cudaFuncSetAttribute(gqa_decode_kernel, cudaFuncAttributeMaxDynamicSharedMemorySize, kSmemTotal);
        void* sp = nullptr;
        cudaGetSymbolAddress(&sp, g_scratch);
        scratch = (Scratch*)sp;
    }
    const uint64_t kv_rows = (uint64_t)kB * kHKV * kSK;
    CUtensorMap tmK, tmV, tmWq, tmWo;
    make_map(encode, &tmK, kc, kDH, kv_rows, 64, kTile, CU_TENSOR_MAP_SWIZZLE_128B, CU_TENSOR_MAP_L2_PROMOTION_L2_256B);
    make_map(encode, &tmV, vc, kDH, kv_rows, 64, kTile, CU_TENSOR_MAP_SWIZZLE_128B, CU_TENSOR_MAP_L2_PROMOTION_L2_256B);
    make_map(encode, &tmWq, wq, kHQ * kDH, kD, 64, 256, CU_TENSOR_MAP_SWIZZLE_128B, CU_TENSOR_MAP_L2_PROMOTION_L2_128B);
    {
        cuuint64_t dims[4] = {(cuuint64_t)kD, 2, 8, (cuuint64_t)kHQ * kDH / 16};
        cuuint64_t strides[3] = {(cuuint64_t)kD * 2 * 8, (cuuint64_t)kD * 2, (cuuint64_t)kD * 2 * 16};
        cuuint32_t box[4] = {64, 2, 8, (cuuint32_t)kWoKs};
        cuuint32_t estr[4] = {1, 1, 1, 1};
        encode(&tmWo, CU_TENSOR_MAP_DATA_TYPE_BFLOAT16, 4, const_cast<void*>(wo), dims, strides, box, estr,
               CU_TENSOR_MAP_INTERLEAVE_NONE, CU_TENSOR_MAP_SWIZZLE_128B, CU_TENSOR_MAP_L2_PROMOTION_L2_256B,
               CU_TENSOR_MAP_FLOAT_OOB_FILL_NONE);
    }

    gqa_decode_kernel<<<kNCTA, kThreads, kSmemTotal>>>(tmK, tmV, tmWq, tmWo, x, (const __nv_bfloat16*)wq,
                                                       (__nv_bfloat16*)d_out, scratch);
}
```
